```python
import torch

def _softmax(x, axis=-1):
    return torch.softmax(x, dim=axis)
def _gelu(x):
    return torch.nn.functional.gelu(x, approximate="tanh")
def _silu(x):
    return torch.nn.functional.silu(x)
def _sigmoid(x):
    return torch.sigmoid(x)
def _layernorm(x, axis=-1, eps=1e-5):
    m = x.mean(dim=axis, keepdim=True)
    v = x.var(dim=axis, keepdim=True, unbiased=False)
    return (x - m) / torch.sqrt(v + eps)
def _scatter_add(tgt, idx, src, axis=0):
    return tgt.clone().index_add_(axis, idx, src)
def _segment_sum(src, seg, n):
    out = torch.zeros((n,) + src.shape[1:], dtype=src.dtype)
    return out.index_add_(0, seg, src)
def _pad(x, pw):
    flat = tuple(v for pair in reversed(pw) for v in pair)
    return torch.nn.functional.pad(x, flat)

kernel_name = 'recurrent_scan__ssm_conv_s5__mixer_s_mlp__prompt'

def setup_inputs():

    _w = (lambda a: (lambda t: t.to(torch.bfloat16) if t.is_floating_point() else t)(torch.as_tensor(a)))
    def _A_setup():
        B, S, D = 1, 2048, 512
        P = D
        Lambda_re = -0.5 * (lambda _x: torch.exp(torch.as_tensor(_x)))((lambda *s: torch.randn(*s, dtype=torch.bfloat16) * 0.2)(P))
        Lambda_im = (lambda *s: torch.randn(*s, dtype=torch.bfloat16) * 0.4)(P) * 1.0
        B_re = (lambda *s: torch.randn(*s, dtype=torch.bfloat16) * 0.2)(P, D) * (D ** -0.5)
        B_im = (lambda *s: torch.randn(*s, dtype=torch.bfloat16) * 0.2)(P, D) * (D ** -0.5)
        C_re = (lambda *s: torch.randn(*s, dtype=torch.bfloat16) * 0.2)(D, P) * (P ** -0.5)
        C_im = (lambda *s: torch.randn(*s, dtype=torch.bfloat16) * 0.2)(D, P) * (P ** -0.5)
        log_dt = (lambda *s: torch.randn(*s, dtype=torch.bfloat16) * 0.2)(P) * 0.3 - 2.0
        Dskip = (lambda *s: torch.randn(*s, dtype=torch.bfloat16) * 0.05)(D)
        return {
            "x": _w((lambda *s: torch.randn(*s, dtype=torch.bfloat16) * 0.05)(B, S, D)),
            "Lambda_re": _w(Lambda_re),
            "Lambda_im": _w(Lambda_im),
            "B_re": _w(B_re),
            "B_im": _w(B_im),
            "C_re": _w(C_re),
            "C_im": _w(C_im),
            "log_dt": _w(log_dt),
            "Dskip": _w(Dskip),
        }
    _A_in = _A_setup()

    def _B_setup():
        B, S, D, F = 1, 2048, 512, 1792
        return {
            "x":  _w((lambda *s: torch.randn(*s, dtype=torch.bfloat16) * 0.05)(B, S, D)),
            "w1": _w((lambda *s: torch.randn(*s, dtype=torch.bfloat16) * 3.2)(D, D) * (D ** -0.5)),
            "w2": _w((lambda *s: torch.randn(*s, dtype=torch.bfloat16) * 3.2)(D, D) * (D ** -0.5)),
            "w3": _w((lambda *s: torch.randn(*s, dtype=torch.bfloat16) * 3.2)(D, F) * (D ** -0.5)),
            "w4": _w((lambda *s: torch.randn(*s, dtype=torch.bfloat16) * 3.2)(F, D) * (F ** -0.5)),
        }
    _B_in = _B_setup()

    return {
        "A_x": _A_in["x"],
        "A_Lambda_re": _A_in["Lambda_re"],
        "A_Lambda_im": _A_in["Lambda_im"],
        "A_B_re": _A_in["B_re"],
        "A_B_im": _A_in["B_im"],
        "A_C_re": _A_in["C_re"],
        "A_C_im": _A_in["C_im"],
        "A_log_dt": _A_in["log_dt"],
        "A_Dskip": _A_in["Dskip"],
        "B_x": _B_in["x"],
        "B_w1": _B_in["w1"],
        "B_w2": _B_in["w2"],
        "B_w3": _B_in["w3"],
        "B_w4": _B_in["w4"],
    }

def reference(A_x, A_Lambda_re, A_Lambda_im, A_B_re, A_B_im, A_C_re, A_C_im, A_log_dt, A_Dskip, B_x, B_w1, B_w2, B_w3, B_w4):
    def _A_ref(x, Lambda_re, Lambda_im, B_re, B_im, C_re, C_im, log_dt, Dskip):
        Bsz, L, H = x.shape
        Lam = Lambda_re + 1j * Lambda_im
        Bmat = B_re + 1j * B_im
        Cmat = C_re + 1j * C_im
        dt = torch.exp(log_dt)
        Lam_bar = torch.exp(dt * Lam)
        B_bar = ((Lam_bar - 1.0) / Lam)[:, None] * Bmat
        Bu = torch.einsum("bld,pd->blp", x + 0j, B_bar)
        h = torch.zeros_like(Bu[:, 0, :])
        hs = []
        for t in range(L):
            h = Lam_bar[None, :] * h + Bu[:, t, :]
            hs.append(h)
        hseq = torch.stack(hs, 1)
        y = 2.0 * torch.einsum("blp,dp->bld", hseq, Cmat).real + x * Dskip[None, None, :]
        return y

    def _B_ref(x, w1, w2, w3, w4):
        B, S, D = x.shape
        h = _gelu(_layernorm(x, axis=-1) @ w1)
        c = D // 4
        g0 = _pad(h[:, :, 0*c:1*c], ((0, 0), (1, 0), (0, 0)))[:, :S, :]
        g1 = _pad(h[:, :, 1*c:2*c], ((0, 0), (0, 1), (0, 0)))[:, 1:, :]
        g2 = _pad(h[:, :, 2*c:3*c], ((0, 0), (2, 0), (0, 0)))[:, :S, :]
        g3 = _pad(h[:, :, 3*c:   ], ((0, 0), (0, 2), (0, 0)))[:, 2:, :]
        hs = torch.concatenate([g0, g1, g2, g3], axis=-1) @ w2
        x1 = x + hs
        h2 = _gelu(_layernorm(x1, axis=-1) @ w3) @ w4
        return x1 + h2

    x = A_x
    xn = _layernorm(x, axis=-1)
    s = _A_ref(xn, A_Lambda_re, A_Lambda_im, A_B_re, A_B_im, A_C_re, A_C_im, A_log_dt, A_Dskip)
    g = _silu(_B_ref(xn, B_w1, B_w2, B_w3, B_w4))
    return x + s * g
```

```cpp
#include <cuda_runtime.h>
#include <cuda_bf16.h>
#include <cuda.h>
#include <stdint.h>

namespace {

constexpr int SEQ = 2048, DM = 512;
constexpr int NW = 8, WSZ = 8192;
constexpr int NTHREADS = 512, MAX_BLK = 15, SC_PER_BLK = 60, MAX_ASZ = 19 * 1024;
constexpr int STAGGER = 250, W_DELAY = 300, PF_STEP = 8, HS_AFTER = 27, CH_AFTER = 30, W_EARLY = 2, X_LEAD = 8;

constexpr int B_AFREE = 192, B_READY = 208, B_EARLY = 216, B_SFIN = 224, B_GFIN = 225, B_SCN = 226, B_FIN = 228, B_POUT = 230, B_ST1 = 231;
constexpr int B_STORED = 232, B_XOWN = 240, B_ST3 = 242, B_PART = 243, NBAR = 245;

template <int G> struct Cfg {
  static constexpr int T = 8 * G, RT = T - 2, TQ = 2 * G, NACC = 4 * G, WN = (G + 1) / 2, CPC = 2 * WN;
  static constexpr int STRIDE = RT - 4, NBLK = (SEQ - RT + STRIDE - 1) / STRIDE + 1, LAST = SEQ - RT - (NBLK - 2) * STRIDE;
  static constexpr int ASZ = 1024 * G, ABYTES = RT * 128, NA = (G == 18 ? 6 : 5) + (NW == 6);
  static constexpr int ACT = 1024, W = ACT + NA * ASZ, STG = W + NW * WSZ + (G & 1) * 1024;
  static constexpr int ST1 = STG + 2 * ASZ, STX = ST1 + 16, ST3 = ST1 + 80 * 32;
  static constexpr int POUT = ST3 + 80 * 32;
  static constexpr int PIN = POUT + 1280;
  static constexpr int SCN = PIN + 1280;
  static constexpr int BAR = SCN + 4096, SMEM = BAR + NBAR * 8 + 1024;
  static_assert(SMEM <= 232448, "smem");
};

struct Maps { CUtensorMap xa, xb, w1, w2, w3, w4, bm, cre, cim; };
struct Ptrs {
  const __nv_bfloat16 *x, *w1, *lre, *lim, *logdt, *dskip, *bre, *bim, *w2, *w3, *cre, *cim, *w4;
  float* out;
  unsigned char* scratch;
  uint4* carry;
  unsigned int* ctr;
  int im_first;
};

__device__ __align__(1024) unsigned char g_scratch[(size_t)MAX_BLK * SC_PER_BLK * MAX_ASZ];
__device__ uint4 g_carry[MAX_BLK * 512];
__device__ __align__(16) unsigned int g_ctr[4];

template<int TA> __device__ __forceinline__ void wgmma(float (&d)[76], uint64_t da, uint64_t db) {
  asm volatile("wgmma.mma_async.sync.aligned.m64n152k16.f32.bf16.bf16 {%0, %1, %2, %3, %4, %5, %6, %7, %8, %9, %10, %11, %12, %13, %14, %15, %16, %17, %18, %19, %20, %21, %22, %23, %24, %25, %26, %27, %28, %29, %30, %31, %32, %33, %34, %35, %36, %37, %38, %39, %40, %41, %42, %43, %44, %45, %46, %47, %48, %49, %50, %51, %52, %53, %54, %55, %56, %57, %58, %59, %60, %61, %62, %63, %64, %65, %66, %67, %68, %69, %70, %71, %72, %73, %74, %75}, %76, %77, 1, 1, 1, %78, 0;"
    : "+f"(d[0]), "+f"(d[1]), "+f"(d[2]), "+f"(d[3]), "+f"(d[4]), "+f"(d[5]), "+f"(d[6]), "+f"(d[7]), "+f"(d[8]), "+f"(d[9]), "+f"(d[10]), "+f"(d[11]), "+f"(d[12]), "+f"(d[13]), "+f"(d[14]), "+f"(d[15]), "+f"(d[16]), "+f"(d[17]), "+f"(d[18]), "+f"(d[19]), "+f"(d[20]), "+f"(d[21]), "+f"(d[22]), "+f"(d[23]), "+f"(d[24]), "+f"(d[25]), "+f"(d[26]), "+f"(d[27]), "+f"(d[28]), "+f"(d[29]), "+f"(d[30]), "+f"(d[31]), "+f"(d[32]), "+f"(d[33]), "+f"(d[34]), "+f"(d[35]), "+f"(d[36]), "+f"(d[37]), "+f"(d[38]), "+f"(d[39]), "+f"(d[40]), "+f"(d[41]), "+f"(d[42]), "+f"(d[43]), "+f"(d[44]), "+f"(d[45]), "+f"(d[46]), "+f"(d[47]), "+f"(d[48]), "+f"(d[49]), "+f"(d[50]), "+f"(d[51]), "+f"(d[52]), "+f"(d[53]), "+f"(d[54]), "+f"(d[55]), "+f"(d[56]), "+f"(d[57]), "+f"(d[58]), "+f"(d[59]), "+f"(d[60]), "+f"(d[61]), "+f"(d[62]), "+f"(d[63]), "+f"(d[64]), "+f"(d[65]), "+f"(d[66]), "+f"(d[67]), "+f"(d[68]), "+f"(d[69]), "+f"(d[70]), "+f"(d[71]), "+f"(d[72]), "+f"(d[73]), "+f"(d[74]), "+f"(d[75])
    : "l"(da), "l"(db), "n"(TA));
}
template<int TA> __device__ __forceinline__ void wgmma_p(float (&d)[76], uint64_t da, uint64_t db, uint32_t keep) {
  asm volatile("{\n.reg .pred p;\nsetp.ne.u32 p, %79, 0;\nwgmma.mma_async.sync.aligned.m64n152k16.f32.bf16.bf16 {%0, %1, %2, %3, %4, %5, %6, %7, %8, %9, %10, %11, %12, %13, %14, %15, %16, %17, %18, %19, %20, %21, %22, %23, %24, %25, %26, %27, %28, %29, %30, %31, %32, %33, %34, %35, %36, %37, %38, %39, %40, %41, %42, %43, %44, %45, %46, %47, %48, %49, %50, %51, %52, %53, %54, %55, %56, %57, %58, %59, %60, %61, %62, %63, %64, %65, %66, %67, %68, %69, %70, %71, %72, %73, %74, %75}, %76, %77, p, 1, 1, %78, 0;\n}"
    : "+f"(d[0]), "+f"(d[1]), "+f"(d[2]), "+f"(d[3]), "+f"(d[4]), "+f"(d[5]), "+f"(d[6]), "+f"(d[7]), "+f"(d[8]), "+f"(d[9]), "+f"(d[10]), "+f"(d[11]), "+f"(d[12]), "+f"(d[13]), "+f"(d[14]), "+f"(d[15]), "+f"(d[16]), "+f"(d[17]), "+f"(d[18]), "+f"(d[19]), "+f"(d[20]), "+f"(d[21]), "+f"(d[22]), "+f"(d[23]), "+f"(d[24]), "+f"(d[25]), "+f"(d[26]), "+f"(d[27]), "+f"(d[28]), "+f"(d[29]), "+f"(d[30]), "+f"(d[31]), "+f"(d[32]), "+f"(d[33]), "+f"(d[34]), "+f"(d[35]), "+f"(d[36]), "+f"(d[37]), "+f"(d[38]), "+f"(d[39]), "+f"(d[40]), "+f"(d[41]), "+f"(d[42]), "+f"(d[43]), "+f"(d[44]), "+f"(d[45]), "+f"(d[46]), "+f"(d[47]), "+f"(d[48]), "+f"(d[49]), "+f"(d[50]), "+f"(d[51]), "+f"(d[52]), "+f"(d[53]), "+f"(d[54]), "+f"(d[55]), "+f"(d[56]), "+f"(d[57]), "+f"(d[58]), "+f"(d[59]), "+f"(d[60]), "+f"(d[61]), "+f"(d[62]), "+f"(d[63]), "+f"(d[64]), "+f"(d[65]), "+f"(d[66]), "+f"(d[67]), "+f"(d[68]), "+f"(d[69]), "+f"(d[70]), "+f"(d[71]), "+f"(d[72]), "+f"(d[73]), "+f"(d[74]), "+f"(d[75])
    : "l"(da), "l"(db), "n"(TA), "r"(keep));
}
template<int TA> __device__ __forceinline__ void wgmma(float (&d)[72], uint64_t da, uint64_t db) {
  asm volatile("wgmma.mma_async.sync.aligned.m64n144k16.f32.bf16.bf16 {%0, %1, %2, %3, %4, %5, %6, %7, %8, %9, %10, %11, %12, %13, %14, %15, %16, %17, %18, %19, %20, %21, %22, %23, %24, %25, %26, %27, %28, %29, %30, %31, %32, %33, %34, %35, %36, %37, %38, %39, %40, %41, %42, %43, %44, %45, %46, %47, %48, %49, %50, %51, %52, %53, %54, %55, %56, %57, %58, %59, %60, %61, %62, %63, %64, %65, %66, %67, %68, %69, %70, %71}, %72, %73, 1, 1, 1, %74, 0;"
    : "+f"(d[0]), "+f"(d[1]), "+f"(d[2]), "+f"(d[3]), "+f"(d[4]), "+f"(d[5]), "+f"(d[6]), "+f"(d[7]), "+f"(d[8]), "+f"(d[9]), "+f"(d[10]), "+f"(d[11]), "+f"(d[12]), "+f"(d[13]), "+f"(d[14]), "+f"(d[15]), "+f"(d[16]), "+f"(d[17]), "+f"(d[18]), "+f"(d[19]), "+f"(d[20]), "+f"(d[21]), "+f"(d[22]), "+f"(d[23]), "+f"(d[24]), "+f"(d[25]), "+f"(d[26]), "+f"(d[27]), "+f"(d[28]), "+f"(d[29]), "+f"(d[30]), "+f"(d[31]), "+f"(d[32]), "+f"(d[33]), "+f"(d[34]), "+f"(d[35]), "+f"(d[36]), "+f"(d[37]), "+f"(d[38]), "+f"(d[39]), "+f"(d[40]), "+f"(d[41]), "+f"(d[42]), "+f"(d[43]), "+f"(d[44]), "+f"(d[45]), "+f"(d[46]), "+f"(d[47]), "+f"(d[48]), "+f"(d[49]), "+f"(d[50]), "+f"(d[51]), "+f"(d[52]), "+f"(d[53]), "+f"(d[54]), "+f"(d[55]), "+f"(d[56]), "+f"(d[57]), "+f"(d[58]), "+f"(d[59]), "+f"(d[60]), "+f"(d[61]), "+f"(d[62]), "+f"(d[63]), "+f"(d[64]), "+f"(d[65]), "+f"(d[66]), "+f"(d[67]), "+f"(d[68]), "+f"(d[69]), "+f"(d[70]), "+f"(d[71])
    : "l"(da), "l"(db), "n"(TA));
}
template<int TA> __device__ __forceinline__ void wgmma_p(float (&d)[72], uint64_t da, uint64_t db, uint32_t keep) {
  asm volatile("{\n.reg .pred p;\nsetp.ne.u32 p, %75, 0;\nwgmma.mma_async.sync.aligned.m64n144k16.f32.bf16.bf16 {%0, %1, %2, %3, %4, %5, %6, %7, %8, %9, %10, %11, %12, %13, %14, %15, %16, %17, %18, %19, %20, %21, %22, %23, %24, %25, %26, %27, %28, %29, %30, %31, %32, %33, %34, %35, %36, %37, %38, %39, %40, %41, %42, %43, %44, %45, %46, %47, %48, %49, %50, %51, %52, %53, %54, %55, %56, %57, %58, %59, %60, %61, %62, %63, %64, %65, %66, %67, %68, %69, %70, %71}, %72, %73, p, 1, 1, %74, 0;\n}"
    : "+f"(d[0]), "+f"(d[1]), "+f"(d[2]), "+f"(d[3]), "+f"(d[4]), "+f"(d[5]), "+f"(d[6]), "+f"(d[7]), "+f"(d[8]), "+f"(d[9]), "+f"(d[10]), "+f"(d[11]), "+f"(d[12]), "+f"(d[13]), "+f"(d[14]), "+f"(d[15]), "+f"(d[16]), "+f"(d[17]), "+f"(d[18]), "+f"(d[19]), "+f"(d[20]), "+f"(d[21]), "+f"(d[22]), "+f"(d[23]), "+f"(d[24]), "+f"(d[25]), "+f"(d[26]), "+f"(d[27]), "+f"(d[28]), "+f"(d[29]), "+f"(d[30]), "+f"(d[31]), "+f"(d[32]), "+f"(d[33]), "+f"(d[34]), "+f"(d[35]), "+f"(d[36]), "+f"(d[37]), "+f"(d[38]), "+f"(d[39]), "+f"(d[40]), "+f"(d[41]), "+f"(d[42]), "+f"(d[43]), "+f"(d[44]), "+f"(d[45]), "+f"(d[46]), "+f"(d[47]), "+f"(d[48]), "+f"(d[49]), "+f"(d[50]), "+f"(d[51]), "+f"(d[52]), "+f"(d[53]), "+f"(d[54]), "+f"(d[55]), "+f"(d[56]), "+f"(d[57]), "+f"(d[58]), "+f"(d[59]), "+f"(d[60]), "+f"(d[61]), "+f"(d[62]), "+f"(d[63]), "+f"(d[64]), "+f"(d[65]), "+f"(d[66]), "+f"(d[67]), "+f"(d[68]), "+f"(d[69]), "+f"(d[70]), "+f"(d[71])
    : "l"(da), "l"(db), "n"(TA), "r"(keep));
}
template<int TA> __device__ __forceinline__ void wgmma(float (&d)[40], uint64_t da, uint64_t db) {
  asm volatile("wgmma.mma_async.sync.aligned.m64n80k16.f32.bf16.bf16 {%0, %1, %2, %3, %4, %5, %6, %7, %8, %9, %10, %11, %12, %13, %14, %15, %16, %17, %18, %19, %20, %21, %22, %23, %24, %25, %26, %27, %28, %29, %30, %31, %32, %33, %34, %35, %36, %37, %38, %39}, %40, %41, 1, 1, 1, %42, 0;"
    : "+f"(d[0]), "+f"(d[1]), "+f"(d[2]), "+f"(d[3]), "+f"(d[4]), "+f"(d[5]), "+f"(d[6]), "+f"(d[7]), "+f"(d[8]), "+f"(d[9]), "+f"(d[10]), "+f"(d[11]), "+f"(d[12]), "+f"(d[13]), "+f"(d[14]), "+f"(d[15]), "+f"(d[16]), "+f"(d[17]), "+f"(d[18]), "+f"(d[19]), "+f"(d[20]), "+f"(d[21]), "+f"(d[22]), "+f"(d[23]), "+f"(d[24]), "+f"(d[25]), "+f"(d[26]), "+f"(d[27]), "+f"(d[28]), "+f"(d[29]), "+f"(d[30]), "+f"(d[31]), "+f"(d[32]), "+f"(d[33]), "+f"(d[34]), "+f"(d[35]), "+f"(d[36]), "+f"(d[37]), "+f"(d[38]), "+f"(d[39])
    : "l"(da), "l"(db), "n"(TA));
}
template<int TA> __device__ __forceinline__ void wgmma_p(float (&d)[40], uint64_t da, uint64_t db, uint32_t keep) {
  asm volatile("{\n.reg .pred p;\nsetp.ne.u32 p, %43, 0;\nwgmma.mma_async.sync.aligned.m64n80k16.f32.bf16.bf16 {%0, %1, %2, %3, %4, %5, %6, %7, %8, %9, %10, %11, %12, %13, %14, %15, %16, %17, %18, %19, %20, %21, %22, %23, %24, %25, %26, %27, %28, %29, %30, %31, %32, %33, %34, %35, %36, %37, %38, %39}, %40, %41, p, 1, 1, %42, 0;\n}"
    : "+f"(d[0]), "+f"(d[1]), "+f"(d[2]), "+f"(d[3]), "+f"(d[4]), "+f"(d[5]), "+f"(d[6]), "+f"(d[7]), "+f"(d[8]), "+f"(d[9]), "+f"(d[10]), "+f"(d[11]), "+f"(d[12]), "+f"(d[13]), "+f"(d[14]), "+f"(d[15]), "+f"(d[16]), "+f"(d[17]), "+f"(d[18]), "+f"(d[19]), "+f"(d[20]), "+f"(d[21]), "+f"(d[22]), "+f"(d[23]), "+f"(d[24]), "+f"(d[25]), "+f"(d[26]), "+f"(d[27]), "+f"(d[28]), "+f"(d[29]), "+f"(d[30]), "+f"(d[31]), "+f"(d[32]), "+f"(d[33]), "+f"(d[34]), "+f"(d[35]), "+f"(d[36]), "+f"(d[37]), "+f"(d[38]), "+f"(d[39])
    : "l"(da), "l"(db), "n"(TA), "r"(keep));
}
template<int TA> __device__ __forceinline__ void wgmma(float (&d)[32], uint64_t da, uint64_t db) {
  asm volatile("wgmma.mma_async.sync.aligned.m64n64k16.f32.bf16.bf16 {%0, %1, %2, %3, %4, %5, %6, %7, %8, %9, %10, %11, %12, %13, %14, %15, %16, %17, %18, %19, %20, %21, %22, %23, %24, %25, %26, %27, %28, %29, %30, %31}, %32, %33, 1, 1, 1, %34, 0;"
    : "+f"(d[0]), "+f"(d[1]), "+f"(d[2]), "+f"(d[3]), "+f"(d[4]), "+f"(d[5]), "+f"(d[6]), "+f"(d[7]), "+f"(d[8]), "+f"(d[9]), "+f"(d[10]), "+f"(d[11]), "+f"(d[12]), "+f"(d[13]), "+f"(d[14]), "+f"(d[15]), "+f"(d[16]), "+f"(d[17]), "+f"(d[18]), "+f"(d[19]), "+f"(d[20]), "+f"(d[21]), "+f"(d[22]), "+f"(d[23]), "+f"(d[24]), "+f"(d[25]), "+f"(d[26]), "+f"(d[27]), "+f"(d[28]), "+f"(d[29]), "+f"(d[30]), "+f"(d[31])
    : "l"(da), "l"(db), "n"(TA));
}
template<int TA> __device__ __forceinline__ void wgmma_p(float (&d)[32], uint64_t da, uint64_t db, uint32_t keep) {
  asm volatile("{\n.reg .pred p;\nsetp.ne.u32 p, %35, 0;\nwgmma.mma_async.sync.aligned.m64n64k16.f32.bf16.bf16 {%0, %1, %2, %3, %4, %5, %6, %7, %8, %9, %10, %11, %12, %13, %14, %15, %16, %17, %18, %19, %20, %21, %22, %23, %24, %25, %26, %27, %28, %29, %30, %31}, %32, %33, p, 1, 1, %34, 0;\n}"
    : "+f"(d[0]), "+f"(d[1]), "+f"(d[2]), "+f"(d[3]), "+f"(d[4]), "+f"(d[5]), "+f"(d[6]), "+f"(d[7]), "+f"(d[8]), "+f"(d[9]), "+f"(d[10]), "+f"(d[11]), "+f"(d[12]), "+f"(d[13]), "+f"(d[14]), "+f"(d[15]), "+f"(d[16]), "+f"(d[17]), "+f"(d[18]), "+f"(d[19]), "+f"(d[20]), "+f"(d[21]), "+f"(d[22]), "+f"(d[23]), "+f"(d[24]), "+f"(d[25]), "+f"(d[26]), "+f"(d[27]), "+f"(d[28]), "+f"(d[29]), "+f"(d[30]), "+f"(d[31])
    : "l"(da), "l"(db), "n"(TA), "r"(keep));
}
template<int TA> __device__ __forceinline__ void wgmma(float (&d)[12], uint64_t da, uint64_t db) {
  asm volatile("wgmma.mma_async.sync.aligned.m64n24k16.f32.bf16.bf16 {%0, %1, %2, %3, %4, %5, %6, %7, %8, %9, %10, %11}, %12, %13, 1, 1, 1, %14, 0;"
    : "+f"(d[0]), "+f"(d[1]), "+f"(d[2]), "+f"(d[3]), "+f"(d[4]), "+f"(d[5]), "+f"(d[6]), "+f"(d[7]), "+f"(d[8]), "+f"(d[9]), "+f"(d[10]), "+f"(d[11])
    : "l"(da), "l"(db), "n"(TA));
}
template<int TA> __device__ __forceinline__ void wgmma_p(float (&d)[12], uint64_t da, uint64_t db, uint32_t keep) {
  asm volatile("{\n.reg .pred p;\nsetp.ne.u32 p, %15, 0;\nwgmma.mma_async.sync.aligned.m64n24k16.f32.bf16.bf16 {%0, %1, %2, %3, %4, %5, %6, %7, %8, %9, %10, %11}, %12, %13, p, 1, 1, %14, 0;\n}"
    : "+f"(d[0]), "+f"(d[1]), "+f"(d[2]), "+f"(d[3]), "+f"(d[4]), "+f"(d[5]), "+f"(d[6]), "+f"(d[7]), "+f"(d[8]), "+f"(d[9]), "+f"(d[10]), "+f"(d[11])
    : "l"(da), "l"(db), "n"(TA), "r"(keep));
}
template<int TA> __device__ __forceinline__ void wgmma(float (&d)[4], uint64_t da, uint64_t db) {
  asm volatile("wgmma.mma_async.sync.aligned.m64n8k16.f32.bf16.bf16 {%0, %1, %2, %3}, %4, %5, 1, 1, 1, %6, 0;"
    : "+f"(d[0]), "+f"(d[1]), "+f"(d[2]), "+f"(d[3])
    : "l"(da), "l"(db), "n"(TA));
}
template<int TA> __device__ __forceinline__ void wgmma_p(float (&d)[4], uint64_t da, uint64_t db, uint32_t keep) {
  asm volatile("{\n.reg .pred p;\nsetp.ne.u32 p, %7, 0;\nwgmma.mma_async.sync.aligned.m64n8k16.f32.bf16.bf16 {%0, %1, %2, %3}, %4, %5, p, 1, 1, %6, 0;\n}"
    : "+f"(d[0]), "+f"(d[1]), "+f"(d[2]), "+f"(d[3])
    : "l"(da), "l"(db), "n"(TA), "r"(keep));
}


__device__ __forceinline__ uint32_t clk32() { uint32_t c; asm volatile("mov.u32 %0, %%clock;" : "=r"(c)); return c; }
__device__ __forceinline__ uint32_t smem_u32(const void* p) { return (uint32_t)__cvta_generic_to_shared(p); }
__device__ __forceinline__ void mbar_init(uint32_t bar, uint32_t cnt) { asm volatile("mbarrier.init.shared::cta.b64 [%0], %1;" ::"r"(bar), "r"(cnt) : "memory"); }
__device__ __forceinline__ void mbar_expect(uint32_t bar, uint32_t bytes) { asm volatile("mbarrier.arrive.expect_tx.shared::cta.b64 _, [%0], %1;" ::"r"(bar), "r"(bytes) : "memory"); }
__device__ __forceinline__ void mbar_arrive(uint32_t bar) { asm volatile("mbarrier.arrive.shared::cta.b64 _, [%0];" ::"r"(bar) : "memory"); }
__device__ __forceinline__ void mbar_arrive_cl(uint32_t cl_addr, uint32_t cnt = 1) { asm volatile("mbarrier.arrive.shared::cluster.b64 _, [%0], %1;" ::"r"(cl_addr), "r"(cnt) : "memory"); }
__device__ __forceinline__ void mbar_wait(uint32_t bar) {
#pragma unroll 1
  for (int i = 0; i < (1 << 20); i++) {
    uint32_t ok;
    asm volatile("{\n.reg .pred p;\nmbarrier.try_wait.parity.shared::cta.b64 p, [%1], 0;\nselp.u32 %0, 1, 0, p;\n}" : "=r"(ok) : "r"(bar) : "memory");
    if (ok) return;
  }
  __trap();
}
__device__ __forceinline__ void mbar_spin(uint32_t bar) {
  asm volatile("{\n.reg .pred p;\nSPIN_%=:\nmbarrier.try_wait.parity.shared::cta.b64 p, [%0], 0;\n@!p bra SPIN_%=;\n}" ::"r"(bar) : "memory");
}
__device__ __forceinline__ uint32_t mbar_test(uint32_t bar) {
  uint32_t ok;
  asm volatile("{\n.reg .pred p;\nmbarrier.test_wait.parity.shared::cta.b64 p, [%1], 0;\nselp.u32 %0, 1, 0, p;\n}" : "=r"(ok) : "r"(bar) : "memory");
  return ok;
}
__device__ __forceinline__ uint32_t mapa(uint32_t addr, uint32_t rank) {
  uint32_t r; asm("mapa.shared::cluster.u32 %0, %1, %2;" : "=r"(r) : "r"(addr), "r"(rank)); return r;
}
__device__ __forceinline__ void wg_fence() { asm volatile("wgmma.fence.sync.aligned;" ::: "memory"); }
__device__ __forceinline__ void wg_commit() { asm volatile("wgmma.commit_group.sync.aligned;" ::: "memory"); }
template <int N> __device__ __forceinline__ void wg_wait() { asm volatile("wgmma.wait_group.sync.aligned %0;" ::"n"(N) : "memory"); }
template <int N> __device__ __forceinline__ void reg_fence(float (&d)[N]) {
#pragma unroll
  for (int i = 0; i < N; i++) asm volatile("" : "+f"(d[i])::"memory");
}
template <int N> __device__ __forceinline__ void fresh(float (&d)[N]) {
#pragma unroll
  for (int i = 0; i < N; i++) asm volatile("mov.b32 %0, 0;" : "=f"(d[i]));
}
__device__ __forceinline__ uint32_t mkdesc(uint32_t addr) { return ((addr & 0x3FFFF) >> 4) | (1u << 16); }
__device__ __forceinline__ uint64_t desc64(uint32_t lo) { return (uint64_t)lo | 0x4000004000000000ull; }
__device__ __forceinline__ void tma2d(uint32_t dst, const CUtensorMap* m, uint32_t bar, int c0, int c1) {
  asm volatile("cp.async.bulk.tensor.2d.shared::cluster.global.mbarrier::complete_tx::bytes [%0], [%1, {%3, %4}], [%2];"
               ::"r"(dst), "l"(m), "r"(bar), "r"(c0), "r"(c1) : "memory");
}
__device__ __forceinline__ void tma4d(uint32_t dst, const CUtensorMap* m, uint32_t bar, int c0, int c3, uint16_t mask) {
  asm volatile("cp.async.bulk.tensor.4d.shared::cluster.global.mbarrier::complete_tx::bytes.multicast::cluster [%0], [%1, {%3, %4, %4, %5}], [%2], %6;"
               ::"r"(dst), "l"(m), "r"(bar), "r"(c0), "r"(0), "r"(c3), "h"(mask) : "memory");
}
__device__ __forceinline__ void bulk_load_mc(uint32_t dst, const void* src, uint32_t bytes, uint32_t bar, uint16_t mask) {
  asm volatile("cp.async.bulk.shared::cluster.global.mbarrier::complete_tx::bytes.multicast::cluster [%0], [%1], %2, [%3], %4;"
               ::"r"(dst), "l"(src), "r"(bytes), "r"(bar), "h"(mask) : "memory");
}
__device__ __forceinline__ void bulk_store(void* dst, uint32_t src, uint32_t bytes) {
  asm volatile("cp.async.bulk.global.shared::cta.bulk_group [%0], [%1], %2;" ::"l"(dst), "r"(src), "r"(bytes) : "memory");
  asm volatile("cp.async.bulk.commit_group;" ::: "memory");
}
__device__ __forceinline__ void l2_prefetch(const void* p, uint32_t bytes) {
  asm volatile("cp.async.bulk.prefetch.L2.global [%0], %1;" ::"l"(p), "r"(bytes) : "memory");
}
__device__ __forceinline__ void stsm4t(uint32_t addr, uint32_t a, uint32_t b, uint32_t c, uint32_t d) {
  asm volatile("stmatrix.sync.aligned.m8n8.x4.trans.shared.b16 [%0], {%1, %2, %3, %4};" ::"r"(addr), "r"(a), "r"(b), "r"(c), "r"(d) : "memory");
}
__device__ __forceinline__ void stsm2t(uint32_t addr, uint32_t a, uint32_t b) {
  asm volatile("stmatrix.sync.aligned.m8n8.x2.trans.shared.b16 [%0], {%1, %2};" ::"r"(addr), "r"(a), "r"(b) : "memory");
}
__device__ __forceinline__ void ldsm4t(uint32_t addr, uint32_t& a, uint32_t& b, uint32_t& c, uint32_t& d) {
  asm volatile("ldmatrix.sync.aligned.m8n8.x4.trans.shared.b16 {%0, %1, %2, %3}, [%4];" : "=r"(a), "=r"(b), "=r"(c), "=r"(d) : "r"(addr) : "memory");
}
__device__ __forceinline__ float4 lds128(uint32_t addr) {
  float4 v; asm volatile("ld.shared.v4.f32 {%0, %1, %2, %3}, [%4];" : "=f"(v.x), "=f"(v.y), "=f"(v.z), "=f"(v.w) : "r"(addr) : "memory"); return v;
}
__device__ __forceinline__ void sts128(uint32_t addr, float a, float b, float c, float d) {
  asm volatile("st.shared.v4.f32 [%0], {%1, %2, %3, %4};" ::"r"(addr), "f"(a), "f"(b), "f"(c), "f"(d) : "memory");
}
__device__ __forceinline__ uint32_t pack_bf16(float lo, float hi) {
  uint32_t r; asm("cvt.rn.bf16x2.f32 %0, %1, %2;" : "=r"(r) : "f"(hi), "f"(lo)); return r;
}
__device__ __forceinline__ float bf_lo(uint32_t v) { return __uint_as_float(v << 16); }
__device__ __forceinline__ float bf_hi(uint32_t v) { return __uint_as_float(v & 0xFFFF0000u); }
__device__ __forceinline__ float bf_round(float v) { return __uint_as_float(pack_bf16(0.f, v)); }
__device__ __forceinline__ float silu_f(float v) {
  const float h = 0.5f * v;
  float t;
  asm("tanh.approx.f32 %0, %1;" : "=f"(t) : "f"(h));
  return fmaf(h, t, h);
}
__device__ __forceinline__ void fence_async_smem() { asm volatile("fence.proxy.async.shared::cta;" ::: "memory"); }
__device__ __forceinline__ float2 cmul(float2 a, float2 b) { return make_float2(fmaf(a.x, b.x, -a.y * b.y), fmaf(a.x, b.y, a.y * b.x)); }
__device__ __forceinline__ float2 cfma(float2 a, float2 b, float2 c) {
  return make_float2(fmaf(a.x, b.x, fmaf(-a.y, b.y, c.x)), fmaf(a.x, b.y, fmaf(a.y, b.x, c.y)));
}

__device__ __forceinline__ int step_nw(int n) {
  return n >= 84 ? 0 : (n < 24 || n >= 56) ? 1 : (n >= 40 && (n & 1)) ? 0 : 2;
}

__host__ __device__ constexpr int first_fill(int n) { return n <= 8 ? n : n <= 24 ? n + 8 : n == 32 ? 48 : n == 40 ? 64 : 80; }
template <int G, int MODE, bool ZERO, int NA1, int NB>
__device__ __forceinline__ void mma_pass(float (&acc)[NA1], float (&accb)[NB], uint32_t base, int step0, int nsteps, int hoff) {
  using C = Cfg<G>;
  constexpr int NA = C::NA;
  constexpr int LAG = 1;
  constexpr bool TWO = MODE == 0 || MODE >= 3;
  const bool lead = (threadIdx.x & 31) == 0;
  const uint32_t dw = mkdesc(base + C::W), d0 = mkdesc(base + C::ACT), d1 = d0 + NA * (C::ASZ / 16);
  uint32_t db = d0 + (step0 % NA) * (C::ASZ / 16), wo = (first_fill(step0) % NW) * (WSZ / 16);
  uint32_t fb = base + C::BAR + step0 * 16;
  const uint32_t fb0 = fb, fb1 = fb + (nsteps - 1) * 16;
  mbar_spin(fb);
#pragma unroll 1
  while (true) {
    const uint64_t da = desc64(dw + wo), db8 = desc64(db), dh8 = desc64(db + hoff);
    wg_fence();
#pragma unroll
    for (int kk = 0; kk < 4; kk++) {
      constexpr int TA = MODE == 1 || MODE >= 3;
      const uint64_t a1 = da + (MODE == 0 ? kk * 2 : MODE == 2 ? (kk >> 1) * (WSZ / 16) + (kk & 1) * 2 : kk * 128);
      if (ZERO && kk == 0) wgmma_p<TA>(acc, a1, db8, fb - fb0); else wgmma<TA>(acc, a1, db8 + kk * 2);
      if constexpr (TWO) {
        if (kk == 0) wgmma_p<TA>(accb, a1 + WSZ / 16, MODE == 4 ? dh8 : db8, fb - fb0);
        else wgmma<TA>(accb, a1 + WSZ / 16, (MODE == 4 ? dh8 : db8) + kk * 2);
      }
    }
    wg_commit();
    const uint32_t ok = mbar_test(fb + 16);
    db += C::ASZ / 16;
    if (db == d1) db = d0;
    if (MODE == 2) wo = (wo ^ 4) + ((wo & 4) << 8);
    else wo += (TWO ? 2 : 1) * (WSZ / 16);
    if (wo == NW * WSZ / 16) wo = 0;
    wg_wait<LAG>();
    if (fb - fb0 >= 16 * LAG && lead) mbar_arrive(fb + 8 - 16 * LAG);
    if (fb == fb1) break;
    fb += 16;
    if (!ok) mbar_spin(fb);
  }
  if (LAG == 2) { wg_wait<1>(); if (lead) mbar_arrive(fb - 8); }
  wg_wait<0>();
  reg_fence(acc);
  if constexpr (TWO) reg_fence(accb);
  if (lead) mbar_arrive(fb + 8);
}
template <int G, bool NORM>
__device__ __forceinline__ void init_from_block(float (&acc)[4 * G], uint32_t img, uint32_t stx) {
  uint32_t xs[4 * Cfg<G>::WN];
#pragma unroll
  for (int j = 0; j < G; j += 2) ldsm4t(img + j * 1024, xs[2 * j], xs[2 * j + 1], xs[2 * j + 2], xs[2 * j + 3]);
#pragma unroll
  for (int j = 0; j < G; j++) {
    acc[4 * j] = bf_lo(xs[2 * j]); acc[4 * j + 1] = bf_hi(xs[2 * j]); acc[4 * j + 2] = bf_lo(xs[2 * j + 1]); acc[4 * j + 3] = bf_hi(xs[2 * j + 1]);
    if (NORM) {
      const float4 s = lds128(stx + j * 128);
      acc[4 * j] = fmaf(acc[4 * j], s.x, -s.y); acc[4 * j + 1] = fmaf(acc[4 * j + 1], s.z, -s.w);
      acc[4 * j + 2] = fmaf(acc[4 * j + 2], s.x, -s.y); acc[4 * j + 3] = fmaf(acc[4 * j + 3], s.z, -s.w);
    }
  }
  reg_fence(acc);
}
template <int G>
__device__ __forceinline__ void store_tile(uint32_t stg, uint32_t lm_off, const uint32_t (&pk)[2 * G]) {
#pragma unroll
  for (int j = 0; j + 1 < G; j += 2) stsm4t(stg + lm_off + j * 1024, pk[2 * j], pk[2 * j + 1], pk[2 * j + 2], pk[2 * j + 3]);
  if (G & 1) stsm2t(stg + (lm_off & 1023) + (G - 1) * 1024, pk[2 * G - 2], pk[2 * G - 1]);
}
__device__ __forceinline__ void publish_tile(uint32_t bars, int id, bool early, bool full) {
  fence_async_smem();
  __syncwarp();
  if ((threadIdx.x & 31) == 0) {
    if (early) mbar_arrive(bars + (B_EARLY + id) * 8);
    if (full) mbar_arrive(bars + (B_READY + id) * 8);
  }
  __syncwarp();
}
template <int WN, int OFF, int GS, int LATE, int N>
__device__ __forceinline__ void gelu_math(const float (&v)[N], uint32_t (&pk)[2 * WN], uint32_t sa, float cs0, float cs1, uint32_t zmask) {
  float zd = 0.f;
#pragma unroll
  for (int hb = 0; hb < 2; hb++) {
    constexpr int J0 = 5;
    const int jn = hb ? WN - J0 : J0;
    float4 s[J0];
#pragma unroll
    for (int j = 0; j < J0; j++) if (j < jn) s[j] = lds128(sa + (J0 * hb + j) * 128);
#pragma unroll
    for (int i = 0; i < 2 * J0; i++) if (i < 2 * jn) {
      const int o = 2 * J0 * hb + i;
      const float4 sj = s[i >> 1];
      const float cs = (i & 1) ? cs1 : cs0;
      const uint32_t h = pack_bf16(fmaf(sj.x, v[OFF + 2 * o], -fmaf(sj.y, cs, zd)), fmaf(sj.z, v[OFF + 2 * o + 1], -fmaf(sj.w, cs, zd)));
      uint32_t u, z, th;
      asm("{\n.reg .b32 t;\nmul.bf16x2 t, %1, %1;\nfma.rn.bf16x2 %0, t, %2, %3;\n}" : "=r"(u) : "r"(h), "r"(0x3E923E92u), "r"(0x3FCC3FCCu));
      asm("mul.bf16x2 %0, %1, %2;" : "=r"(z) : "r"(h), "r"(u));
      asm("tanh.approx.bf16x2 %0, %1;" : "=r"(th) : "r"(z));
      asm("fma.rn.bf16x2 %0, %1, %2, %1;" : "=r"(pk[o]) : "r"(h), "r"(th));
      if (GS < 40 && (o % GS) == GS - 1) zd = __uint_as_float((LATE ? z : h) & zmask);
    }
  }
}
template <int WN>
__device__ __forceinline__ void store_window(const uint32_t (&pk)[2 * WN], uint32_t af, uint32_t am, uint32_t al) {
  stsm4t(af, pk[0], pk[1], pk[2], pk[3]);
#pragma unroll
  for (int i = 1; i < 4; i++) stsm4t(am + (i - 1) * 2048, pk[4 * i], pk[4 * i + 1], pk[4 * i + 2], pk[4 * i + 3]);
  if constexpr (WN == 10) stsm4t(al, pk[16], pk[17], pk[18], pk[19]); else stsm2t(al, pk[16], pk[17]);
}
template <int G, bool HALF, int GS, int LATE>
__device__ __forceinline__ void gelu_windows(float (&acc)[4 * G], const float (&acch)[40], uint32_t bars, uint32_t st_addr, uint32_t a0,
                                             uint32_t dummy, int id0, int odd, uint32_t zmask) {
  constexpr int WN = Cfg<G>::WN, NV = 4 * WN, NH = 4 * G - NV;
  const int lane = threadIdx.x & 31;
  float cs0 = __shfl_sync(0xffffffffu, acc[4 * G - 4], lane | 3), cs1 = __shfl_sync(0xffffffffu, acc[4 * G - 2], lane | 3);
  float csb0 = 0.f, csb1 = 0.f;
  if (HALF) { csb0 = __shfl_sync(0xffffffffu, odd ? acch[36] : acch[0], lane | 3); csb1 = __shfl_sync(0xffffffffu, odd ? acch[38] : acch[2], lane | 3); }
#pragma unroll 1
  for (int win = 0; win < (HALF ? 3 : 2); win++) {
    const int j0 = (HALF && win == 2) ? (odd ? 9 : 9 - WN) : win * WN;
    uint32_t af = a0 + j0 * 1024, al = af + 8192;
    const uint32_t am = af + 2048;
    if (WN == 10) { if ((win & 1) && lane >= 16) al = dummy; if (j0 < 0 && lane < 16) af = dummy; }
    const int id = id0 + (win >> 1);
    uint32_t pk[2 * WN];
    gelu_math<WN, 0, GS, LATE>(acc, pk, st_addr + j0 * 128, cs0, cs1, zmask);
    if (!HALF || win == 0) {
#pragma unroll
      for (int i = 0; i < NH; i++) acc[i] = acc[NV + i];
    } else {
#pragma unroll
      for (int i = 0; i < NV; i++) acc[i] = acch[40 - NV + i];
      cs0 = csb0; cs1 = csb1;
    }
    if (!(win & 1)) mbar_spin(bars + (B_STORED + id - 1) * 8);
    store_window<WN>(pk, af, am, al);
    publish_tile(bars, id, !(win & 1), win != 0);
  }
}
template <int G, bool HALF, int GS, int LATE>
__device__ __forceinline__ void gelu_flat(float (&acc)[4 * G], const float (&acch)[40], uint32_t bars, uint32_t st_addr, uint32_t a0,
                                          uint32_t dummy, int id0, int odd, uint32_t zmask) {
  static_assert(G == 18 || G == 19, "");
  constexpr int WN = Cfg<G>::WN;
  const int lane = threadIdx.x & 31;
  const float cs0 = __shfl_sync(0xffffffffu, acc[4 * G - 4], lane | 3), cs1 = __shfl_sync(0xffffffffu, acc[4 * G - 2], lane | 3);
  {
    uint32_t pk[2 * WN];
    gelu_math<WN, 0, GS, LATE>(acc, pk, st_addr, cs0, cs1, zmask);
    mbar_spin(bars + (B_STORED + id0 - 1) * 8);
    store_window<WN>(pk, a0, a0 + 2048, a0 + 8192);
    publish_tile(bars, id0, true, false);
  }
  {
    uint32_t pk[18];
    gelu_math<9, 4 * WN, GS, LATE>(acc, pk, st_addr + WN * 128, cs0, cs1, zmask);
    store_window<9>(pk, a0 + WN * 1024, a0 + WN * 1024 + 2048, a0 + WN * 1024 + 8192);
    publish_tile(bars, id0, false, true);
  }
  if (HALF) {
    const float c0 = __shfl_sync(0xffffffffu, odd ? acch[36] : acch[0], lane | 3), c1 = __shfl_sync(0xffffffffu, odd ? acch[38] : acch[2], lane | 3);
    const int j0 = odd ? 9 : 9 - WN;
    const uint32_t af = a0 + j0 * 1024;
    uint32_t pk[2 * WN];
    gelu_math<WN, 40 - 4 * WN, GS, LATE>(acch, pk, st_addr + j0 * 128, c0, c1, zmask);
    mbar_spin(bars + (B_STORED + id0) * 8);
    store_window<WN>(pk, (j0 < 0 && lane < 16) ? dummy : af, af + 2048, af + 8192);
    publish_tile(bars, id0 + 1, true, true);
  }
}
__device__ __forceinline__ float ln_rinv(float var) {
  float sq, rs;
  asm("sqrt.approx.ftz.f32 %0, %1;" : "=f"(sq) : "f"(bf_round(bf_round(var) + 1e-5f)));
  asm("rcp.approx.ftz.f32 %0, %1;" : "=f"(rs) : "f"(bf_round(sq)));
  return rs;
}
__device__ __forceinline__ void dsmem_copy(uint32_t dst, uint32_t src, uint32_t bytes, uint32_t bar, uint32_t cta) {
  asm volatile("cp.async.bulk.shared::cluster.shared::cta.mbarrier::complete_tx::bytes [%0], [%1], %2, [%3];"
               ::"r"(mapa(dst, cta)), "r"(src), "r"(bytes), "r"(mapa(bar, cta)) : "memory");
}
struct Gram {
  float d[2][32], d2[12], e[3][4];
};
template <int UNR>
__device__ __forceinline__ void gram_issue(Gram& m, uint32_t base, uint32_t img) {
  const uint64_t di = desc64(mkdesc(img)), dg = desc64(mkdesc(base));
#pragma unroll UNR
  for (int kk = 0; kk < 8; kk += 2) {
    wg_fence();
#pragma unroll
    for (int i = 0; i < 3; i++) {
      const uint64_t da = di + i * 512 + kk;
      if (i < 2) wgmma_p<0>(m.d[i], da, da, kk); else wgmma_p<0>(m.d2, da, da, kk);
      wgmma_p<0>(m.e[i], da, dg + kk, kk);
    }
    wg_commit();
  }
}
__device__ __forceinline__ void gram_pick(Gram& m, float (&o)[12]) {
  const int w = (threadIdx.x >> 5) & 3, g1 = (threadIdx.x >> 2) & 1;
  reg_fence(m.d2);
#pragma unroll
  for (int i = 0; i < 3; i++) {
    if (i < 2) reg_fence(m.d[i]);
    reg_fence(m.e[i]);
    float lo[2], hi[2];
#pragma unroll
    for (int u = 0; u < 2; u++) {
      if (i < 2) {
        lo[u] = w == 0 ? m.d[i][u] : w == 1 ? m.d[i][8 + u] : w == 2 ? m.d[i][16 + u] : m.d[i][24 + u];
        hi[u] = w == 0 ? m.d[i][6 + u] : w == 1 ? m.d[i][14 + u] : w == 2 ? m.d[i][22 + u] : m.d[i][30 + u];
      } else { lo[u] = w == 0 ? m.d2[u] : m.d2[8 + u]; hi[u] = m.d2[6 + u]; }
    }
    o[4 * i] = g1 ? lo[1] : lo[0]; o[4 * i + 1] = g1 ? hi[1] : hi[0]; o[4 * i + 2] = m.e[i][0]; o[4 * i + 3] = m.e[i][2];
  }
}
__device__ __forceinline__ void gram_store(const float (&v)[12], uint32_t pout) {
  const int lane = threadIdx.x & 31, w = (threadIdx.x >> 5) & 3, g = lane >> 2, q = lane & 3;
#pragma unroll
  for (int i = 0; i < 3; i++) {
    const uint32_t o = pout + (64 * i + 16 * w + g) * 8;
    if (i < 2 || w < 2) {
      if (q == (g >> 1)) {
        asm volatile("st.shared.f32 [%0], %1;" ::"r"(o + 4), "f"(v[4 * i]) : "memory");
        asm volatile("st.shared.f32 [%0], %1;" ::"r"(o + 68), "f"(v[4 * i + 1]) : "memory");
      }
      if (q == 3) {
        asm volatile("st.shared.f32 [%0], %1;" ::"r"(o), "f"(v[4 * i + 2]) : "memory");
        asm volatile("st.shared.f32 [%0], %1;" ::"r"(o + 64), "f"(v[4 * i + 3]) : "memory");
      }
    }
  }
  fence_async_smem();
}

template <int G>
__device__ __forceinline__ void scan_consts(uint32_t dst, int im_first, float lr, float li, float ldt, bool short_end) {
  using C = Cfg<G>;
  const float dt = bf_round(expf(ldt));
  const float e = expf(dt * lr);
  float sn, cs; sincospif(dt * li * 0.31830988618379067f, &sn, &cs);
  const float ar = e * cs, ai = e * sn;
  const float nr = ar - 1.f, ni = ai, den = __fdividef(2.f, lr * lr + li * li);
  const float cr = (nr * lr + ni * li) * den, ci = (ni * lr - nr * li) * den;
  const float2 lam = make_float2(ar, im_first ? -ai : ai);
  asm volatile("st.shared.v2.f32 [%0], {%1, %2};" ::"r"(dst), "f"(lam.x), "f"(lam.y) : "memory");
  asm volatile("st.shared.v2.f32 [%0], {%1, %2};" ::"r"(dst + 24), "f"(im_first ? -ci : cr), "f"(im_first ? cr : -ci) : "memory");
#pragma unroll 1
  for (int i = 0; i < 5; i++) {
    int ex = i == 0 ? C::TQ : i == 1 ? (short_end ? C::LAST : C::STRIDE) - 3 * C::TQ : i == 2 ? C::STRIDE : i == 3 ? 4 * C::STRIDE : C::LAST;
    float2 p = make_float2(1.f, 0.f), sq = lam;
#pragma unroll 1
    for (; ex; ex >>= 1) { if (ex & 1) p = cmul(p, sq); sq = cmul(sq, sq); }
    asm volatile("st.shared.v2.f32 [%0], {%1, %2};" ::"r"(dst + 8 + 8 * i + (i >= 2 ? 8 : 0)), "f"(p.x), "f"(p.y) : "memory");
  }
}
__device__ __forceinline__ float2 shfl2(float2 v, int src) { return make_float2(__shfl_sync(0xffffffffu, v.x, src), __shfl_sync(0xffffffffu, v.y, src)); }

template <int G>
__global__ void __launch_bounds__(NTHREADS, 1) fused_kernel(const __grid_constant__ Ptrs P, const __grid_constant__ Maps M) {
  using C = Cfg<G>;
  constexpr int NA = C::NA;
  constexpr int ASZ = C::ASZ, ABYTES = C::ABYTES, RT = C::RT, TQ = C::TQ, WN = C::WN, CPC = C::CPC, NBLK = C::NBLK, NACC = C::NACC;
  static_assert(C::LAST > 3 * TQ && !(C::LAST & 1), "block geometry");
  extern __shared__ __align__(1024) unsigned char smem_raw[];
  const uint32_t base = __shfl_sync(0xffffffffu, (smem_u32(smem_raw) + 1023u) & ~1023u, 0);
  const uint32_t bars = base + C::BAR;
  const int tid = threadIdx.x, lane = tid & 31;
  const int warp = __shfl_sync(0xffffffffu, tid >> 5, 0);
  const int r = blockIdx.x & 7, b = blockIdx.x >> 3;
  const int s0 = min(b * C::STRIDE, SEQ - RT);
  unsigned char* const scr = P.scratch + (size_t)b * SC_PER_BLK * ASZ;
  constexpr int PF = ((524288 / (NBLK * 8) + 127) & ~127), PF3 = ((1835008 / (NBLK * 8) + 127) & ~127);
  const int pf_off = min((int)blockIdx.x * PF, 524288 - 16), pf_len = max(16, min(PF, 524288 - pf_off));
  auto load_x = [&](uint32_t dst, uint32_t bar, uint16_t mask) {
    tma4d(dst, &M.xa, bar, 64 * r, s0 >> 1, mask);
    tma4d(dst + (G - 1) * 1024, &M.xb, bar, 64 * r, (s0 >> 1) + G - 1, mask);
  };
  auto init_steps = [&](int n0, int nw) {
#pragma unroll
    for (int i = 0; i < 8; i++) { mbar_init(bars + (n0 + i) * 16, 1); mbar_init(bars + (n0 + i) * 16 + 8, 4); }
#pragma unroll
    for (int i = 0; i < 8; i++) mbar_expect(bars + (n0 + i) * 16, ABYTES + nw * WSZ);
  };

  if (lane == 0) {
    if (warp == 15) {
      l2_prefetch(P.x + (size_t)(s0 + G * r) * DM, (r == 7 ? G - 2 : G) * 1024);
      l2_prefetch((const char*)P.w1 + pf_off, pf_len);
      asm volatile("prefetch.tensormap [%0];" ::"l"(&M.w1) : "memory");
      asm volatile("prefetch.tensormap [%0];" ::"l"(&M.bm) : "memory");
    } else if (warp == 8) {
      mbar_init(bars + B_XOWN * 8, 1);
      mbar_expect(bars + B_XOWN * 8, ABYTES);
      fence_async_smem();
      load_x(base + C::STG + ASZ, bars + B_XOWN * 8, (uint16_t)(1u << r));
      init_steps(0, 1);
      fence_async_smem();
#pragma unroll
      for (int m = 0; m < W_EARLY; m++) tma2d(base + C::W + m * WSZ, &M.w1, bars + m * 16, 64 * r, 64 * m);
    } else if (warp == 13) {
      l2_prefetch(P.lre, 1024); l2_prefetch(P.lim, 1024); l2_prefetch(P.logdt, 1024); l2_prefetch(P.dskip, 1024);
    } else if (warp == 9) {
      init_steps(8, 2);
    } else if (warp == 14) {
#pragma unroll
      for (int i = 0; i < 3; i++) mbar_init(bars + (B_ST3 + i) * 8, 2);
      const uint32_t tx = RT * 16 - (r == 7 ? RT - 7 * CPC : CPC) * 16;
      mbar_expect(bars + B_ST3 * 8, tx);
      mbar_expect(bars + B_PART * 8, 7 * C::T * 8); mbar_expect(bars + (B_PART + 1) * 8, 7 * CPC * 8);
    } else if (warp < 6) {
      const uint32_t cnt = warp < 2 ? 8 : warp < 5 ? 4 : 1;
#pragma unroll
      for (int i = 0; i < 8; i++) mbar_init(bars + (B_AFREE + warp * 8 + i) * 8, cnt);
    }
  }
  {
    const int t2 = tid - 320;
    if (t2 >= 0 && t2 < (NA + 1) * 16) {
      const uint32_t v = (t2 & 8) ? 0u : 0x3F803F80u;
      asm volatile("st.shared.v4.u32 [%0], {%1, %1, %1, %1};" ::"r"(base + (t2 >> 4) * ASZ + 768 + (t2 & 15) * 16), "r"(v) : "memory");
    } else if (t2 >= 0 && t2 < (NA + 1) * 16 + 3) {
      const int i = t2 - (NA + 1) * 16;
      sts128(base + C::ST1 + (i >> 1) * 2560 + (i & 1) * 16 + (RT / 2) * 32, 0.f, 0.f, 0.f, 0.f);
    }
  }
  const int touch = ((const int*)&P)[12 + 16 * (warp & 1)];
  fence_async_smem();
  asm volatile("fence.mbarrier_init.release.cluster;" ::: "memory");
  __syncthreads();
  asm volatile("barrier.cluster.arrive.relaxed.aligned;" ::"r"(touch) : "memory");
  if (warp == 9) {
    asm volatile("barrier.cluster.wait.aligned;" ::: "memory");
    if (lane == 0) {
#pragma unroll 1
      for (int m = W_EARLY; m < NW; m++) {
        if (m == max(W_EARLY, r - X_LEAD) && r < NA) load_x(base + C::ACT + r * ASZ, bars + r * 16, 0xFF);
        tma2d(base + C::W + m * WSZ, &M.w1, bars + m * 16, 64 * r, 64 * m);
      }
    }
    __syncwarp();
  }

  auto store_block = [&](int id) {
    const int blk = id == 7 ? 56 + (r >> 1) : 8 * ((0x76215430 >> (4 * id)) & 15) + r;
    unsigned char* dst = scr + (size_t)blk * ASZ;
    const uint32_t src = base + C::STG + (id >> 2) * ASZ;
    const int c0 = (id == 7 && (r & 1)) ? 4 : 0, c1 = (id == 7 && !(r & 1)) ? 4 : 6;
    mbar_wait(bars + (B_EARLY + id) * 8);
    if (id == 4) mbar_wait(bars + HS_AFTER * 16);
    if (id == 1) { mbar_wait(bars + (B_READY + id) * 8); bulk_store(dst, src, ABYTES); }
    else
#pragma unroll 1
    for (int c = c0; c < c1; c++) {
      const uint32_t off = ((0xE98051 >> (4 * c)) & 15) * 1024, len = c == 5 ? ABYTES - 14 * 1024 : ((0x051134 >> (4 * c)) & 15) * 1024;
      if (c == 2) mbar_wait(bars + (B_READY + id) * 8);
      bulk_store(dst + off, src + off, len);
      if (id) asm volatile("cp.async.bulk.wait_group.read 1;" ::: "memory");
    }
    asm volatile("cp.async.bulk.wait_group 0;" ::: "memory");
    mbar_arrive(bars + (B_STORED + id) * 8);
  };
  if (warp >= 8) {
    asm volatile("setmaxnreg.dec.sync.aligned.u32 24;");
    if (warp == 12 || warp == 14) {
      const int n0 = warp == 12 ? 16 : 56;
      if (lane == 0) {
#pragma unroll 1
        for (int n = n0; n < n0 + 40; n += 4) {
#pragma unroll
          for (int i = 0; i < 4; i++) { mbar_init(bars + (n + i) * 16, 1); mbar_init(bars + (n + i) * 16 + 8, 4); }
        }
      }
      __syncwarp();
      mbar_expect(bars + (n0 + lane) * 16, ABYTES + step_nw(n0 + lane) * WSZ);
      if (lane < 8) mbar_expect(bars + (n0 + 32 + lane) * 16, ABYTES + step_nw(n0 + 32 + lane) * WSZ);
      fence_async_smem();
      asm volatile("fence.mbarrier_init.release.cluster;" ::: "memory");
      __syncwarp();
    }
    if (warp == 10 || warp == 13) {
      const int t = warp & 1, pp = 256 * t + 32 * r + lane;
      scan_consts<G>(base + C::SCN + (t * 32 + lane) * 64, P.im_first, __bfloat162float(P.lre[pp]), __bfloat162float(P.lim[pp]),
                     __bfloat162float(P.logdt[pp]), C::LAST != C::STRIDE && b == NBLK - 2);
      __syncwarp();
      if (lane < 2) mbar_arrive(bars + B_SCN * 8);
    }
    if (warp >= 12) asm volatile("barrier.cluster.wait.aligned;" ::: "memory");
    if (warp != 15 && lane != 0) return;
    if (warp == 12 || warp == 14) {
      int n = 0;
#pragma unroll 1
      for (int e = 0; e < 12; e++) {
        const bool own = e >= 11;
        const int cnt = own ? 1 : e == 9 ? 4 : 8;
        uint32_t ta = mapa(bars + (B_AFREE + e) * 8, own ? r : 0);
#pragma unroll 1
        for (int k = 0; k < cnt; k++, n++, ta += 1u << 24) {
          if (n < NA || ((n ^ (warp >> 1)) & 1)) { if (e == 9) ta += 1u << 24; continue; }
          mbar_wait(bars + (n - NA) * 16 + 8);
          mbar_arrive_cl(ta, own ? 8 : 1);
          if (e == 9) { ta += 1u << 24; mbar_arrive_cl(ta); }
        }
      }
    } else if (warp == 10 || warp == 13) {
#pragma unroll 1
      for (int id = (warp & 1) * 4; id < (warp & 1) * 4 + 4; id++) store_block(id);
      if (warp == 13) load_x(base + C::STG + ASZ, bars + 85 * 16, (uint16_t)(1u << r));
    } else if (warp == 15) {
      auto pf_lines = [&](const void* p, int off, int len) {
#pragma unroll 1
        for (int o = lane * 128; o < len; o += 4096) asm volatile("prefetch.global.L2 [%0];" ::"l"((const char*)p + off + o));
      };
      mbar_wait(bars + B_XOWN * 8);
      {
        const int o3 = blockIdx.x * PF3, l3 = min(PF3, 1835008 - o3);
#pragma unroll 1
        for (int i = 0; i < 5; i++) {
          if (i == 1) mbar_wait(bars + PF_STEP * 16);
          const bool big = i == 1 || i == 4;
          pf_lines((&P.w2)[i], big ? o3 : pf_off, big ? l3 : pf_len);
        }
        if (lane < 5) asm volatile("prefetch.tensormap [%0];" ::"l"(lane < 3 ? &M.w2 + lane : &M.cre + (lane - 3)) : "memory");
      }
      __syncwarp();
      const uint32_t pbar = bars + (B_PART + 1) * 8;
      mbar_wait(bars + B_POUT * 8);
      if (lane < 8) {
        if (lane == r) mbar_arrive(pbar);
        else dsmem_copy(base + C::PIN + r * 160, base + C::POUT + lane * CPC * 8, CPC * 8, pbar, lane);
      }
      __syncwarp();
      mbar_wait(pbar);
      const int i = min(lane, CPC - 1);
      float sx = 0.f, sq = 0.f;
      const uint32_t ib = base + C::PIN + i * 8, io = base + C::POUT + r * CPC * 8 + i * 8;
#pragma unroll
      for (int c = 0; c < 8; c++) {
        float a, q2;
        asm volatile("ld.shared.v2.f32 {%0, %1}, [%2];" : "=f"(a), "=f"(q2) : "r"(c ? ib + ((r + c) & 7) * 160 : io) : "memory");
        sx += a; sq += q2;
      }
      const float md = sx * (1.f / 512.f);
      const float r3 = 0.5f * ln_rinv(fmaxf(fmaf(-md, md, sq * (1.f / 512.f)), 0.f));
      const uint32_t chunk = base + C::ST3 + r * CPC * 16, sbar = bars + B_ST3 * 8;
      if (CPC * r + i < RT) asm volatile("st.shared.v2.f32 [%0], {%1, %2};" ::"r"(chunk + (i >> 1) * 32 + (i & 1) * 8), "f"(r3), "f"(bf_round(md) * r3) : "memory");
      fence_async_smem();
      __syncwarp();
      if (lane < 8) {
        if (lane == r) mbar_arrive(sbar);
        else dsmem_copy(chunk, chunk, (r == 7 ? RT - 7 * CPC : CPC) * 16, sbar, lane);
      }
      if (lane != 0) return;
      mbar_wait(bars + (B_READY + 4) * 8);
      const unsigned int old = atomicAdd(P.ctr + 1, 1u);
      if (old == NBLK * 8 - 1) { P.ctr[1] = 0; P.ctr[0] = P.ctr[0] + 1; }
      mbar_wait(bars + B_FIN * 8);
      mbar_wait(bars + (B_FIN + 1) * 8);
    } else if (warp == 9) {
#pragma unroll 1
      for (int e = r < NA ? 1 : 0; e < 12; e++) {
        const bool own = e >= 11;
        const int dep = (int)(0xf376254110ffull >> (4 * e)) & 15, grp = (int)(0x3576421330ffull >> (4 * e)) & 15;
        int step = own ? 84 : (e == 10 ? 76 : 8 * e) + r, blk = 8 * grp + r; uint32_t off = 0, bytes = ABYTES;
        if (e == 9) { step = 72 + (r >> 1); blk = 56 + (r >> 1); off = (r & 1) ? 9216 : 0; bytes = (r & 1) ? ABYTES - 9216 : 9216; }
        const uint16_t mask = (uint16_t)(own ? 1u << r : 0xFFu);
        const uint32_t dst = base + C::ACT + (step % NA) * ASZ + off, fb = bars + step * 16;
        const unsigned char* src = scr + (size_t)blk * ASZ + off;
        const uint32_t delay = ((0xC >> e) & 1) ? (uint32_t)r * STAGGER : 0u;
        if (dep != 15) mbar_wait(bars + (B_STORED + dep) * 8);
        const uint32_t t_dep = clk32();
        mbar_wait(bars + (B_AFREE + e) * 8);
        while (clk32() - t_dep < delay) {}
        if (grp == 15) load_x(dst, fb, mask); else bulk_load_mc(dst, src, bytes, fb, mask);
      }
    } else {
      const int hf = warp & 1;
      __nanosleep(W_DELAY);
      l2_prefetch((const char*)(hf ? P.bre : P.bim) + pf_off, pf_len);
      uint32_t wo = hf * WSZ;
      uint32_t rel = (0x06040200u + hf * 0x01010101u) & (NW == 6 ? 0xFFFFFFu : 0xFFFFFFFFu);
#pragma unroll 1
      for (int sg = NW == 6 ? 0 : 1; sg < 7; sg++) {
        const CUtensorMap* mp; int c0 = 64 * r, c1 = 64 * hf, step = 8 * sg;
        if (sg == 0) { step = 6 + hf; mp = &M.w1; c1 += 384; }
        else if (sg == 1) { mp = &M.bm; c0 = 0; c1 = 32 * hf + 4 * r; }
        else if (sg == 2) { step += hf; mp = &M.w2; }
        else if (sg == 5) { mp = hf ? &M.cim : &M.cre; c0 = 0; c1 = 64 * r; }
        else if (sg == 6) { step = 56 + hf; mp = &M.w4; }
        else { mp = &M.w3; c1 = 0; c0 = 64 * (sg == 3 ? 20 * hf + r : hf ? 16 + (r >> 1) : 8 + r); }
        const bool four = sg == 1, w3 = sg == 3 || sg == 4;
        const int d0 = (four || sg == 5) ? 64 : 0, d1 = (four || sg == 5) ? 0 : w3 ? 64 : 128, dstep = (w3 || four) ? 1 : 2, cnt = sg == 0 ? 1 : sg == 2 ? 4 : sg == 6 ? 14 : 8;
#pragma unroll 1
        for (int k = 0; k < cnt; k++) {
          const uint32_t dst = base + C::W + wo, fb = bars + step * 16;
          mbar_wait(bars + (rel & 255) * 16 + 8);
          if (four) tma4d(dst, mp, fb, c0, c1, (uint16_t)(1u << r)); else tma2d(dst, mp, fb, c0, c1);
          rel = (rel >> 8) | ((uint32_t)(step + (sg == 5)) << (4 * NW - 8));
          wo += 2 * WSZ;
          if (wo >= NW * WSZ) wo -= NW * WSZ;
          c0 += d0; c1 += d1; step += dstep;
        }
      }
    }
  } else {
    asm volatile("setmaxnreg.inc.sync.aligned.u32 232;");
    const int wg = warp >> 2, w = warp & 3, g = lane >> 2, q = lane & 3;
    const int mi = lane >> 3, li = lane & 7;
    const uint32_t lm_off = (mi >> 1) * 1024 + li * 128 + (((2 * w + (mi & 1)) ^ li) << 4);
    const uint32_t stx = base + C::STX + q * 32;
    const uint32_t stg = base + C::STG + wg * ASZ, dummy = stg + RT * 128 + li * 16;
    const int odd = r & 1;
    const uint32_t zmask = (uint32_t)P.im_first >> 8;
    const uint32_t sbuf = base + C::STG - (G & 1) * 1024 + (tid & 127) * 16;
    const int p0 = 32 * r + 8 * w + g;
    constexpr bool UNI = C::LAST == C::STRIDE;
    const bool short_end = !UNI && b == NBLK - 2, last = !UNI && b == NBLK - 1;
    float acc[NACC];
    float4 sv[WN];
    const uint32_t hand = base + C::ACT + (85 % NA) * ASZ + (tid & 127) * 16;
    const uint32_t st3 = base + C::ST3 + q * 32;
    float acch[40], fv[4 * WN];
    if (wg == 1) {
      asm volatile("barrier.cluster.wait.aligned;" ::: "memory");
      { Gram m;
      mbar_spin(bars + B_XOWN * 8);
      gram_issue<4>(m, base, stg); wg_wait<0>();
        float gv[12];
        gram_pick(m, gv);
        gram_store(gv, base + C::POUT);
        asm volatile("bar.sync 2, 128;" ::: "memory");
        if (lane < 2) {
          const int dd = 2 * w + lane;
          if (dd == r) mbar_arrive(bars + B_PART * 8);
          else dsmem_copy(base + C::STG + r * 1280, base + C::POUT, C::T * 8, bars + B_PART * 8, dd);
        }
        __syncwarp();
      }
      mbar_spin(bars + B_PART * 8);
      {
        const int np = min(tid & 127, RT / 2 - 1);
        float4 sm = make_float4(0.f, 0.f, 0.f, 0.f);
#pragma unroll
        for (int cc = 0; cc < 8; cc++) {
          const float4 a = lds128(base + (cc == r ? C::POUT : C::STG + cc * 1280) + np * 16);
          sm.x += a.x; sm.y += a.y; sm.z += a.z; sm.w += a.w;
        }
        float o[2][4];
#pragma unroll
        for (int u = 0; u < 2; u++) {
          const float md = (u ? sm.z : sm.x) * (1.f / 512.f);
          const float var = fmaxf(fmaf(-md, md, (u ? sm.w : sm.y) * (1.f / 512.f)), 0.f);
          const float m1 = bf_round(md), r1 = ln_rinv(var);
          const float m2 = bf_round((md - m1) * r1), r2 = 0.5f * ln_rinv(var * r1 * r1);
          o[u][0] = r1 * r2; o[u][1] = fmaf(m1, r1, m2) * r2; o[u][2] = r1; o[u][3] = m1 * r1;
        }
        sts128(base + C::ST1 + np * 32, o[0][0], o[0][1], o[1][0], o[1][1]);
        sts128(base + C::ST1 + np * 32 + 16, o[0][2], o[0][3], o[1][2], o[1][3]);
      }
      __syncwarp();
      if (lane == 0) mbar_arrive(bars + B_ST1 * 8);
      uint32_t epoch;
      asm volatile("ld.relaxed.gpu.global.u32 %0, [%1];" : "=r"(epoch) : "l"(P.ctr));
      float accb[NACC];
      mma_pass<G, 0, true>(acc, accb, base, 8, 8, 0);
      epoch += 1;
      mbar_spin(bars + B_SCN * 8);
      mbar_spin(bars + B_ST1 * 8);
      float2 cloc[2];
      {
        float2 lam[2], h[2], he[2];
        float cs[2][2];
#pragma unroll
        for (int t = 0; t < 2; t++) {
          float (&a)[NACC] = t ? accb : acc;
          const float4 c0 = lds128(base + C::SCN + (t * 32 + 8 * w + g) * 64);
          lam[t] = make_float2(c0.x, c0.y); h[t] = he[t] = make_float2(0.f, 0.f);
          cs[t][0] = __shfl_sync(0xffffffffu, a[NACC - 4], lane | 3); cs[t][1] = __shfl_sync(0xffffffffu, a[NACC - 2], lane | 3);
        }
#pragma unroll
        for (int j = 0; j < G; j++) {
          const float4 s = lds128(stx + j * 128);
#pragma unroll
          for (int t = 0; t < 2; t++) {
            float (&a)[NACC] = t ? accb : acc;
            const float z0 = 1 ? __uint_as_float(__float_as_uint(h[1 - t].x) & zmask) : 0.f;
            a[4 * j] = fmaf(s.x, a[4 * j], -fmaf(s.y, cs[t][0], z0)); a[4 * j + 2] = fmaf(s.x, a[4 * j + 2], -fmaf(s.y, cs[t][1], z0));
            a[4 * j + 1] = fmaf(s.z, a[4 * j + 1], -fmaf(s.w, cs[t][0], z0)); a[4 * j + 3] = fmaf(s.z, a[4 * j + 3], -fmaf(s.w, cs[t][1], z0));
            h[t] = cfma(lam[t], h[t], make_float2(a[4 * j], a[4 * j + 2]));
            h[t] = cfma(lam[t], h[t], make_float2(a[4 * j + 1], a[4 * j + 3]));
            if (!UNI && 2 * j + 2 == C::LAST - 3 * TQ) he[t] = h[t];
            if (2 * j + 2 == C::STRIDE - 3 * TQ && !short_end) he[t] = h[t];
          }
        }
        const int lb = lane & ~3;
#pragma unroll
        for (int t = 0; t < 2; t++) {
          const uint32_t so = base + C::SCN + (t * 32 + 8 * w + g) * 64;
          const float4 c0 = lds128(so), c1 = lds128(so + 16);
          const float2 pq = make_float2(c0.z, c0.w), pe = make_float2(c1.x, c1.y);
          const float2 e0 = shfl2(h[t], lb), e1 = shfl2(h[t], lb + 1), e2 = shfl2(h[t], lb + 2);
          const float2 c2 = cfma(pq, e0, e1), c3 = cfma(pq, c2, e2);
          if (q == 3) {
            const float2 E = cfma(pe, c3, he[t]);
            asm volatile("st.relaxed.gpu.global.v4.u32 [%0], {%1, %2, %3, %4};" ::"l"(P.carry + b * 512 + 256 * t + p0), "r"(__float_as_uint(E.x)), "r"(epoch), "r"(__float_as_uint(E.y)), "r"(epoch) : "memory");
          }
          cloc[t] = q == 0 ? make_float2(0.f, 0.f) : q == 1 ? e0 : q == 2 ? c2 : c3;
        }
      }
#pragma unroll 1
      for (int t = 0; t < 2; t++) {
        const uint32_t so = base + C::SCN + (t * 32 + 8 * w + g) * 64;
        const float4 c0 = lds128(so), c1 = lds128(so + 16);
        const float2 lam = make_float2(c0.x, c0.y), pq = make_float2(c0.z, c0.w), kk = make_float2(c1.z, c1.w);
        const uint4* const cp = P.carry + 256 * t + p0;
        const float4 c2v = lds128(so + 32), c3v = lds128(so + 48);
        const float2 ps = make_float2(c2v.x, c2v.y), ps4 = make_float2(c2v.z, c2v.w);
        const float2 ps2 = cmul(ps, ps), pq2 = cmul(pq, pq);
        const float sg = P.im_first ? -1.f : 1.f, k10 = sg * kk.y, k11 = -sg * kk.x;
        float2 wq = q == 0 ? make_float2(1.f, 0.f) : q == 1 ? ps : q == 2 ? ps2 : cmul(ps2, ps);
        const float2 vq = q == 0 ? make_float2(1.f, 0.f) : q == 1 ? pq : q == 2 ? pq2 : cmul(pq2, pq);
        if (last) wq = cmul(wq, make_float2(c3v.x, c3v.y));
        const int bb = last ? b - 1 : b;
        uint4 v[4];
        auto poll = [&]() {
#pragma unroll 1
          for (int it = 0; it < (1 << 21); it++) {
            bool ok = true;
#pragma unroll
            for (int i = 0; i < 4; i++) {
              const int j = (i == 3 && q == 3 && last) ? b - 1 : bb - 1 - q - 4 * i;
              v[i] = make_uint4(0u, epoch, 0u, epoch);
              if (j >= 0) asm volatile("ld.relaxed.gpu.global.v4.u32 {%0, %1, %2, %3}, [%4];" : "=r"(v[i].x), "=r"(v[i].y), "=r"(v[i].z), "=r"(v[i].w) : "l"(cp + j * 512) : "memory");
            }
#pragma unroll
            for (int i = 0; i < 4; i++) ok = ok && v[i].y == epoch && v[i].w == epoch;
            if (__all_sync(0xffffffffu, ok)) return;
          }
          __trap();
        };
        poll();
        const float2 v3 = make_float2(__uint_as_float(v[3].x), __uint_as_float(v[3].z));
        float2 part = q == 3 ? make_float2(0.f, 0.f) : v3;
#pragma unroll
        for (int i = 2; i >= 0; i--) part = cfma(ps4, part, make_float2(__uint_as_float(v[i].x), __uint_as_float(v[i].z)));
        part = cfma(part, wq, q == 3 ? v3 : make_float2(0.f, 0.f));
        part.x += __shfl_xor_sync(0xffffffffu, part.x, 1); part.y += __shfl_xor_sync(0xffffffffu, part.y, 1);
        part.x += __shfl_xor_sync(0xffffffffu, part.x, 2); part.y += __shfl_xor_sync(0xffffffffu, part.y, 2);
        float2 h = cfma(vq, part, cloc[0]);
        float2 l2 = lam;
        uint32_t pk[2 * G];
#pragma unroll
        for (int j = 0; j < G; j++) {
          const float2 h0 = cfma(l2, h, make_float2(acc[4 * j], acc[4 * j + 2]));
          const float y0 = fmaf(kk.x, h0.x, kk.y * h0.y);
          if (1 == 2) l2.y = __uint_as_float(__float_as_uint(lam.y) | (__float_as_uint(y0) & zmask));
          h = cfma(l2, h0, make_float2(acc[4 * j + 1], acc[4 * j + 3]));
          const float y1 = fmaf(kk.x, h.x, kk.y * h.y);
          if (1) l2.y = __uint_as_float(__float_as_uint(lam.y) | (__float_as_uint(y1) & zmask));
          pk[2 * j] = pack_bf16(y0, y1);
          pk[2 * j + 1] = pack_bf16(fmaf(k10, h0.x, k11 * h0.y), fmaf(k10, h.x, k11 * h.y));
        }
        mbar_spin(t ? bars + (B_STORED + 4) * 8 : bars + (B_READY + 1) * 8);
        store_tile<G>(stg, (mi >> 1) * 1024 + li * 128 + (((w + 4 * (mi & 1)) ^ li) << 4), pk);
        publish_tile(bars, 4 + t, true, true);
#pragma unroll
        for (int i = 0; i < NACC; i++) acc[i] = accb[i];
        cloc[0] = cloc[1];
      }
      float accc[NACC];
      mbar_spin(bars + CH_AFTER * 16 + 8);
      mma_pass<G, 4, true>(accc, acch, base, 32, 8, __shfl_sync(0xffffffffu, odd ? (G - 10) * 64 : -64, 0));
      mbar_spin(bars + B_ST3 * 8);
      gelu_windows<G, true, 40, 0>(accc, acch, bars, st3, stg + lm_off, dummy, 6, odd, zmask);
      float accg[NACC];
      mma_pass<G, 1, true>(accg, accg, base, 56, 28, 0);
#pragma unroll
      for (int j = WN; j < G; j++) sts128(hand + (j - WN) * 2048, accg[4 * j], accg[4 * j + 1], accg[4 * j + 2], accg[4 * j + 3]);
      __syncwarp();
      if (lane == 0) mbar_arrive(bars + B_GFIN * 8);
      mbar_spin(bars + B_SFIN * 8);
#pragma unroll
      for (int j = 0; j < WN; j++) sv[j] = lds128(sbuf + j * 2048);
#pragma unroll
      for (int i = 0; i < 4 * WN; i++) fv[i] = accg[i];
    } else {
      {
        const int grp = r >> 1, sh = grp == 0 ? 1 : grp == 1 ? -1 : grp == 2 ? 2 : -2;
        const int chunk = 2 * w + (mi & 1);
        auto shaddr = [&](int jj) {
          int t = 2 * jj + (li & 1) + sh, qq = li >> 1;
          if (t < 0) { t += TQ; qq -= 1; }
          if (t >= TQ) { t -= TQ; qq += 1; }
          const int r7 = 2 * (qq & 3) + (t & 1);
          return stg + (t >> 1) * 1024 + r7 * 128 + ((chunk ^ r7) << 4);
        };
        uint32_t af = shaddr(mi >> 1), am = shaddr(2 + (mi >> 1)), al = am + 6144;
        const uint32_t aend = ((G & 1) && lane >= 16) ? dummy : shaddr(G - 1);
        asm volatile("barrier.cluster.wait.aligned;" ::: "memory");
        mma_pass<G, 1, true>(acc, acc, base, 0, 8, 0);
        const float cs0 = __shfl_sync(0xffffffffu, acc[NACC - 4], lane | 3), cs1 = __shfl_sync(0xffffffffu, acc[NACC - 2], lane | 3);
        mbar_spin(bars + B_ST1 * 8);
#pragma unroll 1
        for (int win = 0; win < 2; win++) {
          uint32_t pk[2 * WN];
          gelu_math<WN, 0, 40, 0>(acc, pk, base + C::ST1 + q * 32 + win * WN * 128, cs0, cs1, 0);
#pragma unroll
          for (int i = 0; i < NACC - 4 * WN; i++) acc[i] = acc[4 * WN + i];
          store_window<WN>(pk, af, am, al);
          publish_tile(bars, win * (B_READY - B_EARLY), true, false);
          af = am + (WN - 2) * 1024; am += WN * 1024; al = aend;
        }
      }
      init_from_block<G, true>(acc, base + C::STG + ASZ + lm_off, stx);
      mma_pass<G, 1, false>(acc, acc, base, 16, 8, 0);
      {
        uint32_t pk[2 * G];
#pragma unroll
        for (int i = 0; i < 2 * G; i++) pk[i] = pack_bf16(acc[2 * i], acc[2 * i + 1]);
        store_tile<G>(stg, lm_off, pk);
        publish_tile(bars, 1, true, true);
        mbar_spin(bars + (1 ? B_STORED + 1 : B_READY + 1) * 8);
        Gram m;
        gram_issue<1>(m, base, stg);
        wg_wait<0>();
        float gv[12];
        gram_pick(m, gv);
        gram_store(gv, base + C::POUT);
        __syncwarp();
        if (lane == 0) mbar_arrive(bars + B_POUT * 8);
        __syncwarp();
      }
      float accb[NACC];
      mma_pass<G, 3, true>(acc, accb, base, 24, 8, 0);
      mbar_spin(bars + B_ST3 * 8);
      gelu_flat<G, false, 40, 0>(acc, acch, bars, st3, stg + lm_off, dummy, 2, 0, zmask);
      float accs[NACC];
      mma_pass<G, 2, true>(accs, accs, base, 40, 16, 0);
      gelu_windows<G, false, 1, 1>(accb, acch, bars, st3, stg + lm_off, dummy, 3, 0, zmask);
      const float dk0 = __bfloat162float(P.dskip[64 * r + 16 * w + g]), dk1 = __bfloat162float(P.dskip[64 * r + 16 * w + 8 + g]);
      mbar_spin(bars + 85 * 16);
#pragma unroll
      for (int j = 0; j < G; j += 2) {
        uint32_t xs[4];
        ldsm4t(base + C::STG + ASZ + lm_off + j * 1024, xs[0], xs[1], xs[2], xs[3]);
#pragma unroll
        for (int u = 0; u < 2; u++) if (j + u < G) {
          const int o = 4 * (j + u);
          const float4 s = lds128(stx + (j + u) * 128);
          if (1 && o) xs[2 * u] |= __float_as_uint(accs[o - 1]) & zmask;
          accs[o] = fmaf(fmaf(bf_lo(xs[2 * u]), s.x, -s.y), dk0, accs[o]); accs[o + 1] = fmaf(fmaf(bf_hi(xs[2 * u]), s.z, -s.w), dk0, accs[o + 1]);
          if (1) xs[2 * u + 1] |= __float_as_uint(accs[o + 1]) & zmask;
          accs[o + 2] = fmaf(fmaf(bf_lo(xs[2 * u + 1]), s.x, -s.y), dk1, accs[o + 2]); accs[o + 3] = fmaf(fmaf(bf_hi(xs[2 * u + 1]), s.z, -s.w), dk1, accs[o + 3]);
        }
      }
      mbar_spin(bars + (B_STORED + 3) * 8);
#pragma unroll
      for (int j = 0; j < WN; j++) sts128(sbuf + j * 2048, accs[4 * j], accs[4 * j + 1], accs[4 * j + 2], accs[4 * j + 3]);
      __syncwarp();
      if (lane == 0) mbar_arrive(bars + B_SFIN * 8);
      if (G & 1) sv[WN - 1] = make_float4(0.f, 0.f, 0.f, 0.f);
#pragma unroll
      for (int j = WN; j < G; j++) sv[j - WN] = make_float4(accs[4 * j], accs[4 * j + 1], accs[4 * j + 2], accs[4 * j + 3]);
          mbar_spin(bars + B_GFIN * 8);
#pragma unroll
      for (int j = 0; j < WN; j++) { const float4 s = lds128(hand + j * 2048); fv[4 * j] = s.x; fv[4 * j + 1] = s.y; fv[4 * j + 2] = s.z; fv[4 * j + 3] = s.w; }
    }
    asm volatile("barrier.cluster.arrive.relaxed.aligned;" ::: "memory");
    mbar_spin(bars + 84 * 16);
    if (lane == 0) mbar_arrive(bars + (B_FIN + wg) * 8);
    __syncwarp();
    {
      const int hw = 1 - wg;
      const int lo = b == 0 ? 0 : 2, t0 = TQ * q + 2 * WN * hw;
      const int hi = min(b == NBLK - 1 ? RT : b == NBLK - 2 ? C::LAST + 2 : C::STRIDE + 2, TQ * q + TQ);
      float* op = P.out + (size_t)(s0 + t0) * DM + 64 * r + 16 * w + g;
      const uint32_t xa = base + lm_off + hw * WN * 1024;
      uint32_t xv[20], yv[20];
#pragma unroll
      for (int i = 0; i < 5; i++) ldsm4t(xa + C::ACT + (84 % NA) * ASZ + i * 2048, yv[4 * i], yv[4 * i + 1], yv[4 * i + 2], yv[4 * i + 3]);
#pragma unroll
      for (int i = 0; i < 5; i++) ldsm4t(xa + C::STG + ASZ + i * 2048, xv[4 * i], xv[4 * i + 1], xv[4 * i + 2], xv[4 * i + 3]);
#pragma unroll
      for (int j = 0; j < WN; j++) {
        const int t = t0 + 2 * j;
        const float o0 = fmaf(sv[j].x, silu_f(fv[4 * j] + bf_lo(yv[2 * j])), bf_lo(xv[2 * j]));
        const float o1 = fmaf(sv[j].y, silu_f(fv[4 * j + 1] + bf_hi(yv[2 * j])), bf_hi(xv[2 * j]));
        const float o2 = fmaf(sv[j].z, silu_f(fv[4 * j + 2] + bf_lo(yv[2 * j + 1])), bf_lo(xv[2 * j + 1]));
        const float o3 = fmaf(sv[j].w, silu_f(fv[4 * j + 3] + bf_hi(yv[2 * j + 1])), bf_hi(xv[2 * j + 1]));
        const uint32_t ok = t >= lo && t < hi;
        asm volatile("{\n.reg .pred p;\nsetp.ne.u32 p, %5, 0;\n@p st.global.f32 [%0], %1;\n@p st.global.f32 [%0+2048], %2;\n@p st.global.f32 [%0+32], %3;\n@p st.global.f32 [%0+2080], %4;\n}"
                     ::"l"(op + 2 * j * DM), "f"(o0), "f"(o1), "f"(o2), "f"(o3), "r"(ok) : "memory");
      }
    }
    asm volatile("barrier.cluster.wait.aligned;" ::: "memory");
  }
}

typedef CUresult (*EncFn)(CUtensorMap*, CUtensorMapDataType, cuuint32_t, void*, const cuuint64_t*, const cuuint64_t*, const cuuint32_t*,
                          const cuuint32_t*, CUtensorMapInterleave, CUtensorMapSwizzle, CUtensorMapL2promotion, CUtensorMapFloatOOBfill);

void enc(EncFn fn, CUtensorMap* m, const void* p, int rank, const cuuint64_t* dims, const cuuint64_t* str, const cuuint32_t* box) {
  const cuuint32_t es[4] = {1, 1, 1, 1};
  fn(m, CU_TENSOR_MAP_DATA_TYPE_BFLOAT16, rank, (void*)p, dims, str, box, es, CU_TENSOR_MAP_INTERLEAVE_NONE, CU_TENSOR_MAP_SWIZZLE_128B,
     CU_TENSOR_MAP_L2_PROMOTION_L2_128B, CU_TENSOR_MAP_FLOAT_OOB_FILL_NONE);
}
void enc2d(EncFn fn, CUtensorMap* m, const void* p, int rows, int cols) {
  const cuuint64_t dims[2] = {(cuuint64_t)cols, (cuuint64_t)rows}, str[1] = {(cuuint64_t)cols * 2};
  const cuuint32_t box[2] = {64, 64};
  enc(fn, m, p, 2, dims, str, box);
}
template <int G> void make_cfg(cudaLaunchConfig_t& cfg, cudaLaunchAttribute* at) {
  cfg = {};
  cfg.gridDim = dim3(Cfg<G>::NBLK * 8); cfg.blockDim = dim3(NTHREADS); cfg.dynamicSmemBytes = Cfg<G>::SMEM; cfg.stream = cudaStreamPerThread;
  at[0].id = cudaLaunchAttributeClusterDimension; at[0].val.clusterDim.x = 8; at[0].val.clusterDim.y = 1; at[0].val.clusterDim.z = 1;
  cfg.attrs = at; cfg.numAttrs = 1;
}

}

extern "C" void kernel_launch(void* const* d_in, const int* in_sizes, int n_in, void* d_out, int out_size) {
  static EncFn fn = nullptr;
  static int G = 0;
  static void *p_scr, *p_carry, *p_ctr;
  cudaLaunchConfig_t cfg; cudaLaunchAttribute at[1];
  if (!fn) {
    void* f = nullptr; cudaDriverEntryPointQueryResult qr;
    cudaGetDriverEntryPoint("cuTensorMapEncodeTiled", &f, cudaEnableDefault, &qr);
    fn = (EncFn)f;
    cudaGetSymbolAddress(&p_scr, g_scratch); cudaGetSymbolAddress(&p_carry, g_carry); cudaGetSymbolAddress(&p_ctr, g_ctr);
    cudaFuncSetAttribute(fused_kernel<18>, cudaFuncAttributeMaxDynamicSharedMemorySize, Cfg<18>::SMEM);
    cudaFuncSetAttribute(fused_kernel<19>, cudaFuncAttributeMaxDynamicSharedMemorySize, Cfg<19>::SMEM);
    make_cfg<18>(cfg, at);
    int nc = 0;
    if (cudaOccupancyMaxActiveClusters(&nc, fused_kernel<18>, &cfg) != cudaSuccess) { nc = 0; (void)cudaGetLastError(); }
    G = nc >= Cfg<18>::NBLK ? 18 : 19;
  }
  Ptrs P;
  P.x = (const __nv_bfloat16*)d_in[0]; P.lre = (const __nv_bfloat16*)d_in[1]; P.lim = (const __nv_bfloat16*)d_in[2];
  P.bre = (const __nv_bfloat16*)d_in[3]; P.bim = (const __nv_bfloat16*)d_in[4]; P.cre = (const __nv_bfloat16*)d_in[5]; P.cim = (const __nv_bfloat16*)d_in[6];
  P.logdt = (const __nv_bfloat16*)d_in[7]; P.dskip = (const __nv_bfloat16*)d_in[8];
  P.w1 = (const __nv_bfloat16*)d_in[10]; P.w2 = (const __nv_bfloat16*)d_in[11]; P.w3 = (const __nv_bfloat16*)d_in[12]; P.w4 = (const __nv_bfloat16*)d_in[13];
  P.out = (float*)d_out;
  P.scratch = (unsigned char*)p_scr; P.carry = (uint4*)p_carry; P.ctr = (unsigned int*)p_ctr;
  P.im_first = P.bim < P.bre;
  Maps M;
  {
    const cuuint64_t dims[4] = {512, 2, 4, 1024}, str[3] = {1024, (cuuint64_t)G * 2048, 2048};
    const cuuint32_t boxa[4] = {64, 2, 4, (cuuint32_t)G - 1}, boxb[4] = {64, 2, 3, 1};
    enc(fn, &M.xa, P.x, 4, dims, str, boxa);
    enc(fn, &M.xb, P.x, 4, dims, str, boxb);
  }
  {
    const __nv_bfloat16* lo = P.im_first ? P.bim : P.bre; const __nv_bfloat16* hi = P.im_first ? P.bre : P.bim;
    const cuuint64_t dims[4] = {512, 8, 2, 64}, str[3] = {1024, (cuuint64_t)((const char*)hi - (const char*)lo), 8192};
    const cuuint32_t box[4] = {64, 8, 2, 4};
    enc(fn, &M.bm, lo, 4, dims, str, box);
  }
  enc2d(fn, &M.w1, P.w1, 512, 512); enc2d(fn, &M.w2, P.w2, 512, 512); enc2d(fn, &M.w3, P.w3, 512, 1792); enc2d(fn, &M.w4, P.w4, 1792, 512);
  enc2d(fn, &M.cre, P.cre, 512, 512); enc2d(fn, &M.cim, P.cim, 512, 512);
  if (G == 18) { make_cfg<18>(cfg, at); cudaLaunchKernelEx(&cfg, fused_kernel<18>, P, M); }
  else { make_cfg<19>(cfg, at); cudaLaunchKernelEx(&cfg, fused_kernel<19>, P, M); }
}
```
